```python
import torch

def _softmax(x, axis=-1):
    return torch.softmax(x, dim=axis)

def _gelu(x):
    return torch.nn.functional.gelu(x, approximate='tanh')

def _silu(x):
    return torch.nn.functional.silu(x)

def _sigmoid(x):
    return torch.sigmoid(x)

def _layernorm(x, axis=-1, eps=1e-05):
    m = x.mean(dim=axis, keepdim=True)
    v = x.var(dim=axis, keepdim=True, unbiased=False)
    return (x - m) / torch.sqrt(v + eps)

def _scatter_add(tgt, idx, src, axis=0):
    return tgt.clone().index_add_(axis, idx, src)

def _segment_sum(src, seg, n):
    out = torch.zeros((n,) + src.shape[1:], dtype=src.dtype)
    return out.index_add_(0, seg, src)

def _pad(x, pw):
    flat = tuple((v for pair in reversed(pw) for v in pair))
    return torch.nn.functional.pad(x, flat)
kernel_name = 'standalone__video_videomae__vision'

def setup_inputs():

    _w = lambda a: (lambda t: t.to(torch.bfloat16) if t.is_floating_point() else t)(torch.as_tensor(a))
    T = 4
    N = 256
    C = max(384 // 4 * 4, 8)
    sc = C ** (-0.5)
    return {'x': _w((lambda *s: torch.randn(*s, dtype=torch.bfloat16) * 1.6)(1, T, N, C)), 'w_qkv_t': _w((lambda *s: torch.randn(*s, dtype=torch.bfloat16) * 1.6)(C, 3 * C) * sc), 'w_proj_t': _w((lambda *s: torch.randn(*s, dtype=torch.bfloat16) * 1.6)(C, C) * sc), 'w_qkv_s': _w((lambda *s: torch.randn(*s, dtype=torch.bfloat16) * 1.6)(C, 3 * C) * sc), 'w_proj_s': _w((lambda *s: torch.randn(*s, dtype=torch.bfloat16) * 0.8)(C, C) * sc), 'w1': _w((lambda *s: torch.randn(*s, dtype=torch.bfloat16) * 0.8)(C, 4 * C) * sc), 'w2': _w((lambda *s: torch.randn(*s, dtype=torch.bfloat16) * 0.8)(4 * C, C) * sc)}

def reference(x, w_qkv_t, w_proj_t, w_qkv_s, w_proj_s, w1, w2):
    B, T, N, C = x.shape
    Hd = 4
    D = C // Hd
    scale = D ** (-0.5)
    h = _layernorm(x, axis=-1)
    qkv = torch.einsum('btnc,ce->btne', h, w_qkv_t).reshape(B, T, N, 3, Hd, D)
    q = qkv[:, :, :, 0, :, :].clone()
    k = qkv[:, :, :, 1, :, :].clone()
    v = qkv[:, :, :, 2, :, :].clone()
    a = torch.einsum('btnhd,bsnhd->bnhts', q, k) * scale
    a = _softmax(a, axis=-1)
    o = torch.einsum('bnhts,bsnhd->btnhd', a, v).reshape(B, T, N, C)
    x = x + torch.einsum('btnc,ce->btne', o, w_proj_t)
    h = _layernorm(x, axis=-1)
    qkv = torch.einsum('btnc,ce->btne', h, w_qkv_s).reshape(B, T, N, 3, Hd, D)
    q = qkv[:, :, :, 0, :, :].clone()
    k = qkv[:, :, :, 1, :, :].clone()
    v = qkv[:, :, :, 2, :, :].clone()
    a = torch.einsum('btnhd,btmhd->bthnm', q, k) * scale
    a = _softmax(a, axis=-1)
    o = torch.einsum('bthnm,btmhd->btnhd', a, v).reshape(B, T, N, C)
    x = x + torch.einsum('btnc,ce->btne', o, w_proj_s)
    h = _layernorm(x, axis=-1)
    return x + _gelu(h @ w1) @ w2
```

```cpp
#include <cuda_runtime.h>
#include <cuda_bf16.h>
#include <cuda.h>
#include <stdint.h>

namespace vm {

constexpr uint32_t SLOT = 49152;
constexpr uint32_t OFF_STAGE = 4 * SLOT;
constexpr uint32_t OFF_KST = OFF_STAGE, OFF_VST = OFF_STAGE + 6400, OFF_H = OFF_STAGE, OFF_STT = OFF_STAGE + 16384, OFF_CMB = OFF_STAGE;
constexpr uint32_t OFF_RSTD = OFF_STAGE + 24576;
constexpr uint32_t OFF_RES = OFF_RSTD + 256;
constexpr uint32_t OFF_BAR = OFF_RES + 6144;
constexpr uint32_t SMEM_BYTES = OFF_BAR + 64 * 8 + 1024;
constexpr int SPIN = 1 << 18;

enum { FW0 = 0, FX = 14, FT0 = 15  , FQ = 25, FV = 26, FK0 = 27, FK1 = 28,
       EV_X = 29, EV_XL, EV_QK, EV_V, EV_T1, EV_T2, EV_T3, EV_T4, EV_G2, EV_KS, EV_QS, EV_VS, EV_K, EV_PV, EV_G4,
       EV_M0, EV_M1, EV_M2, EV_P0  , FWH = EV_P0 + 6  , NBAR = FWH + 2 };

struct __align__(1024) Scratch {
  uint4 OT[16][24][128];
  uint4 X1[16][24][128];
  uint4 OS[16][24][128];
  uint4 X2[16][24][128];
  uint4 Q[16][4][6][128];
  uint4 K[4][4][3072];
  uint4 V[4][4][2][1536];
  uint4 X1R[16][8][3][128];
  uint4 SC[16][8][128];
  uint4 ST[2][16][8][32];
  unsigned KF[4][32];
  unsigned XF[16][8][8];
  unsigned OF[16][32];
  unsigned epoch[32];
};
__device__ Scratch g_s;
#define TS(i)
#define TSD(i)
#define TS_DUMP()

struct Params {
  CUtensorMap tm_x, tm_wqt, tm_wqt32, tm_wpt, tm_wqs, tm_wps, tm_w1, tm_w2, tm_out;
  const char* wraw[6];
  __nv_bfloat16* out;
};

__device__ __forceinline__ uint32_t smem_u32(const void* p) { return (uint32_t)__cvta_generic_to_shared(p); }
__device__ __forceinline__ void mbar_init(uint32_t bar, uint32_t cnt) { asm volatile("mbarrier.init.shared::cta.b64 [%0], %1;" ::"r"(bar), "r"(cnt)); }
__device__ __forceinline__ void mbar_expect(uint32_t bar, uint32_t bytes) { asm volatile("mbarrier.arrive.expect_tx.shared::cta.b64 _, [%0], %1;" ::"r"(bar), "r"(bytes) : "memory"); }
__device__ __forceinline__ void mbar_arrive(uint32_t bar) { asm volatile("mbarrier.arrive.shared::cta.b64 _, [%0];" ::"r"(bar) : "memory"); }
__device__ __forceinline__ void mbar_wait(uint32_t bar) {
  asm volatile("{\n.reg .pred p;\n.reg .u32 it;\nmov.u32 it, 0;\n"
               "LW:\nmbarrier.try_wait.parity.shared::cta.b64 p, [%0], 0;\n@p bra LD;\n"
               "add.u32 it, it, 1;\nsetp.lt.u32 p, it, %1;\n@p bra LW;\nLD:\n}" ::"r"(bar), "n"(SPIN) : "memory");
}
__device__ __forceinline__ void warp_arrive(uint32_t bar, int lane) { __syncwarp(); if (lane == 0) mbar_arrive(bar); }
__device__ __forceinline__ void tma2d(uint32_t dst, const CUtensorMap* tm, int x, int y, uint32_t bar) {
  asm volatile("cp.async.bulk.tensor.2d.shared::cluster.global.mbarrier::complete_tx::bytes [%0], [%1, {%3, %4}], [%2];"
               ::"r"(dst), "l"(tm), "r"(bar), "r"(x), "r"(y) : "memory");
}
__device__ __forceinline__ void tma3d(uint32_t dst, const CUtensorMap* tm, int x, int y, int z, uint32_t bar) {
  asm volatile("cp.async.bulk.tensor.3d.shared::cluster.global.mbarrier::complete_tx::bytes [%0], [%1, {%3, %4, %5}], [%2];"
               ::"r"(dst), "l"(tm), "r"(bar), "r"(x), "r"(y), "r"(z) : "memory");
}
__device__ __forceinline__ void bulk_g2s(uint32_t dst, const void* src, uint32_t bytes, uint32_t bar) {
  asm volatile("cp.async.bulk.shared::cluster.global.mbarrier::complete_tx::bytes [%0], [%1], %2, [%3];"
               ::"r"(dst), "l"(src), "r"(bytes), "r"(bar) : "memory");
}
__device__ __forceinline__ uint4 ld_rlx(const uint4* p) {
  uint4 v; asm volatile("ld.relaxed.gpu.global.v4.u32 {%0,%1,%2,%3}, [%4];" : "=r"(v.x), "=r"(v.y), "=r"(v.z), "=r"(v.w) : "l"(p) : "memory"); return v;
}
__device__ __forceinline__ uint32_t ld_rlx32(const void* p) {
  uint32_t v; asm volatile("ld.relaxed.gpu.global.u32 %0, [%1];" : "=r"(v) : "l"(p) : "memory"); return v;
}
__device__ __forceinline__ void st_rlx(uint4* p, uint32_t a, uint32_t b, uint32_t c, uint32_t d) {
  asm volatile("st.relaxed.gpu.global.v4.u32 [%0], {%1,%2,%3,%4};" ::"l"(p), "r"(a), "r"(b), "r"(c), "r"(d) : "memory");
}
__device__ __forceinline__ void lds128(uint32_t (&r)[4], uint32_t a) {
  asm volatile("ld.shared.v4.u32 {%0,%1,%2,%3}, [%4];" : "=r"(r[0]), "=r"(r[1]), "=r"(r[2]), "=r"(r[3]) : "r"(a) : "memory");
}
__device__ __forceinline__ void sts128(uint32_t a, uint4 v) {
  asm volatile("st.shared.v4.u32 [%0], {%1,%2,%3,%4};" ::"r"(a), "r"(v.x), "r"(v.y), "r"(v.z), "r"(v.w) : "memory");
}
__device__ __forceinline__ void ldsm4(uint32_t (&r)[4], uint32_t a) {
  asm volatile("ldmatrix.sync.aligned.m8n8.x4.shared.b16 {%0,%1,%2,%3}, [%4];" : "=r"(r[0]), "=r"(r[1]), "=r"(r[2]), "=r"(r[3]) : "r"(a) : "memory");
}
__device__ __forceinline__ void stsm4(uint32_t a, uint32_t r0, uint32_t r1, uint32_t r2, uint32_t r3) {
  asm volatile("stmatrix.sync.aligned.m8n8.x4.shared.b16 [%0], {%1,%2,%3,%4};" ::"r"(a), "r"(r0), "r"(r1), "r"(r2), "r"(r3) : "memory");
}
__device__ __forceinline__ uint32_t movm(uint32_t a) {
  uint32_t d; asm volatile("movmatrix.sync.aligned.m8n8.trans.b16 %0, %1;" : "=r"(d) : "r"(a)); return d;
}
__device__ __forceinline__ void hmma(float (&d)[4], uint32_t a0, uint32_t a1, uint32_t a2, uint32_t a3, uint32_t b0, uint32_t b1) {
  asm volatile("mma.sync.aligned.m16n8k16.row.col.f32.bf16.bf16.f32 {%0,%1,%2,%3}, {%4,%5,%6,%7}, {%8,%9}, {%0,%1,%2,%3};"
               : "+f"(d[0]), "+f"(d[1]), "+f"(d[2]), "+f"(d[3]) : "r"(a0), "r"(a1), "r"(a2), "r"(a3), "r"(b0), "r"(b1));
}
__device__ __forceinline__ uint32_t pk(float lo, float hi) { uint32_t d; asm("cvt.rn.bf16x2.f32 %0, %1, %2;" : "=r"(d) : "f"(hi), "f"(lo)); return d; }
__device__ __forceinline__ float blo(uint32_t w) { return __uint_as_float(w << 16); }
__device__ __forceinline__ float bhi(uint32_t w) { return __uint_as_float(w & 0xffff0000u); }
__device__ __forceinline__ uint32_t hsub2(uint32_t a, uint32_t b) { uint32_t d; asm("sub.rn.bf16x2 %0, %1, %2;" : "=r"(d) : "r"(a), "r"(b)); return d; }
__device__ __forceinline__ float ex2(float x) { float y; asm("ex2.approx.ftz.f32 %0, %1;" : "=f"(y) : "f"(x)); return y; }
__device__ __forceinline__ float rsq(float x) { float y; asm("rsqrt.approx.ftz.f32 %0, %1;" : "=f"(y) : "f"(x)); return y; }
__device__ __forceinline__ float tanh_ap(float x) { float y; asm("tanh.approx.f32 %0, %1;" : "=f"(y) : "f"(x)); return y; }
__device__ __forceinline__ void wg_fence() { asm volatile("wgmma.fence.sync.aligned;" ::: "memory"); }
__device__ __forceinline__ void wg_commit() { asm volatile("wgmma.commit_group.sync.aligned;" ::: "memory"); }
template <int N> __device__ __forceinline__ void wg_wait() { asm volatile("wgmma.wait_group.sync.aligned %0;" ::"n"(N) : "memory"); }
template <int N> __device__ __forceinline__ void reg_fence(float (&d)[N]) {
#pragma unroll
  for (int i = 0; i < N; i++) asm volatile("" : "+f"(d[i])::"memory");
}
__device__ __forceinline__ void wg48_t(float (&d)[24], const uint32_t (&a)[4], uint32_t dlo, uint32_t dhi, int sd) {
  asm volatile("{\n.reg .pred p;\n.reg .b64 db;\nsetp.ne.b32 p, %30, 0;\nmov.b64 db, {%28, %29};\n"
    "wgmma.mma_async.sync.aligned.m64n48k16.f32.bf16.bf16 {%0, %1, %2, %3, %4, %5, %6, %7, %8, %9, %10, %11, %12, %13, %14, %15, %16, %17, %18, %19, %20, %21, %22, %23}, {%24, %25, %26, %27}, db, p, 1, 1, 1;\n}\n"
    : "+f"(d[0]), "+f"(d[1]), "+f"(d[2]), "+f"(d[3]), "+f"(d[4]), "+f"(d[5]), "+f"(d[6]), "+f"(d[7]), "+f"(d[8]), "+f"(d[9]), "+f"(d[10]), "+f"(d[11]), "+f"(d[12]), "+f"(d[13]), "+f"(d[14]), "+f"(d[15]), "+f"(d[16]), "+f"(d[17]), "+f"(d[18]), "+f"(d[19]), "+f"(d[20]), "+f"(d[21]), "+f"(d[22]), "+f"(d[23])
    : "r"(a[0]), "r"(a[1]), "r"(a[2]), "r"(a[3]), "r"(dlo), "r"(dhi), "r"(sd));
}
__device__ __forceinline__ void wg64_t(float (&d)[32], const uint32_t (&a)[4], uint32_t dlo, uint32_t dhi, int sd) {
  asm volatile("{\n.reg .pred p;\n.reg .b64 db;\nsetp.ne.b32 p, %38, 0;\nmov.b64 db, {%36, %37};\n"
    "wgmma.mma_async.sync.aligned.m64n64k16.f32.bf16.bf16 {%0, %1, %2, %3, %4, %5, %6, %7, %8, %9, %10, %11, %12, %13, %14, %15, %16, %17, %18, %19, %20, %21, %22, %23, %24, %25, %26, %27, %28, %29, %30, %31}, {%32, %33, %34, %35}, db, p, 1, 1, 1;\n}\n"
    : "+f"(d[0]), "+f"(d[1]), "+f"(d[2]), "+f"(d[3]), "+f"(d[4]), "+f"(d[5]), "+f"(d[6]), "+f"(d[7]), "+f"(d[8]), "+f"(d[9]), "+f"(d[10]), "+f"(d[11]), "+f"(d[12]), "+f"(d[13]), "+f"(d[14]), "+f"(d[15]), "+f"(d[16]), "+f"(d[17]), "+f"(d[18]), "+f"(d[19]), "+f"(d[20]), "+f"(d[21]), "+f"(d[22]), "+f"(d[23]), "+f"(d[24]), "+f"(d[25]), "+f"(d[26]), "+f"(d[27]), "+f"(d[28]), "+f"(d[29]), "+f"(d[30]), "+f"(d[31])
    : "r"(a[0]), "r"(a[1]), "r"(a[2]), "r"(a[3]), "r"(dlo), "r"(dhi), "r"(sd));
}

__device__ __forceinline__ void wg128_n(float (&d)[64], const uint32_t (&a)[4], uint32_t dlo, uint32_t dhi, int sd) {
  asm volatile("{\n.reg .pred p;\n.reg .b64 db;\nsetp.ne.b32 p, %70, 0;\nmov.b64 db, {%68, %69};\n"
    "wgmma.mma_async.sync.aligned.m64n128k16.f32.bf16.bf16 {%0, %1, %2, %3, %4, %5, %6, %7, %8, %9, %10, %11, %12, %13, %14, %15, %16, %17, %18, %19, %20, %21, %22, %23, %24, %25, %26, %27, %28, %29, %30, %31, %32, %33, %34, %35, %36, %37, %38, %39, %40, %41, %42, %43, %44, %45, %46, %47, %48, %49, %50, %51, %52, %53, %54, %55, %56, %57, %58, %59, %60, %61, %62, %63}, {%64, %65, %66, %67}, db, p, 1, 1, 0;\n}\n"
    : "+f"(d[0]), "+f"(d[1]), "+f"(d[2]), "+f"(d[3]), "+f"(d[4]), "+f"(d[5]), "+f"(d[6]), "+f"(d[7]), "+f"(d[8]), "+f"(d[9]), "+f"(d[10]), "+f"(d[11]), "+f"(d[12]), "+f"(d[13]), "+f"(d[14]), "+f"(d[15]), "+f"(d[16]), "+f"(d[17]), "+f"(d[18]), "+f"(d[19]), "+f"(d[20]), "+f"(d[21]), "+f"(d[22]), "+f"(d[23]), "+f"(d[24]), "+f"(d[25]), "+f"(d[26]), "+f"(d[27]), "+f"(d[28]), "+f"(d[29]), "+f"(d[30]), "+f"(d[31]), "+f"(d[32]), "+f"(d[33]), "+f"(d[34]), "+f"(d[35]), "+f"(d[36]), "+f"(d[37]), "+f"(d[38]), "+f"(d[39]), "+f"(d[40]), "+f"(d[41]), "+f"(d[42]), "+f"(d[43]), "+f"(d[44]), "+f"(d[45]), "+f"(d[46]), "+f"(d[47]), "+f"(d[48]), "+f"(d[49]), "+f"(d[50]), "+f"(d[51]), "+f"(d[52]), "+f"(d[53]), "+f"(d[54]), "+f"(d[55]), "+f"(d[56]), "+f"(d[57]), "+f"(d[58]), "+f"(d[59]), "+f"(d[60]), "+f"(d[61]), "+f"(d[62]), "+f"(d[63])
    : "r"(a[0]), "r"(a[1]), "r"(a[2]), "r"(a[3]), "r"(dlo), "r"(dhi), "r"(sd));
}
__device__ __forceinline__ void wg128_t(float (&d)[64], const uint32_t (&a)[4], uint32_t dlo, uint32_t dhi, int sd) {
  asm volatile("{\n.reg .pred p;\n.reg .b64 db;\nsetp.ne.b32 p, %70, 0;\nmov.b64 db, {%68, %69};\n"
    "wgmma.mma_async.sync.aligned.m64n128k16.f32.bf16.bf16 {%0, %1, %2, %3, %4, %5, %6, %7, %8, %9, %10, %11, %12, %13, %14, %15, %16, %17, %18, %19, %20, %21, %22, %23, %24, %25, %26, %27, %28, %29, %30, %31, %32, %33, %34, %35, %36, %37, %38, %39, %40, %41, %42, %43, %44, %45, %46, %47, %48, %49, %50, %51, %52, %53, %54, %55, %56, %57, %58, %59, %60, %61, %62, %63}, {%64, %65, %66, %67}, db, p, 1, 1, 1;\n}\n"
    : "+f"(d[0]), "+f"(d[1]), "+f"(d[2]), "+f"(d[3]), "+f"(d[4]), "+f"(d[5]), "+f"(d[6]), "+f"(d[7]), "+f"(d[8]), "+f"(d[9]), "+f"(d[10]), "+f"(d[11]), "+f"(d[12]), "+f"(d[13]), "+f"(d[14]), "+f"(d[15]), "+f"(d[16]), "+f"(d[17]), "+f"(d[18]), "+f"(d[19]), "+f"(d[20]), "+f"(d[21]), "+f"(d[22]), "+f"(d[23]), "+f"(d[24]), "+f"(d[25]), "+f"(d[26]), "+f"(d[27]), "+f"(d[28]), "+f"(d[29]), "+f"(d[30]), "+f"(d[31]), "+f"(d[32]), "+f"(d[33]), "+f"(d[34]), "+f"(d[35]), "+f"(d[36]), "+f"(d[37]), "+f"(d[38]), "+f"(d[39]), "+f"(d[40]), "+f"(d[41]), "+f"(d[42]), "+f"(d[43]), "+f"(d[44]), "+f"(d[45]), "+f"(d[46]), "+f"(d[47]), "+f"(d[48]), "+f"(d[49]), "+f"(d[50]), "+f"(d[51]), "+f"(d[52]), "+f"(d[53]), "+f"(d[54]), "+f"(d[55]), "+f"(d[56]), "+f"(d[57]), "+f"(d[58]), "+f"(d[59]), "+f"(d[60]), "+f"(d[61]), "+f"(d[62]), "+f"(d[63])
    : "r"(a[0]), "r"(a[1]), "r"(a[2]), "r"(a[3]), "r"(dlo), "r"(dhi), "r"(sd));
}
__device__ __forceinline__ void wg32_t(float (&d)[16], const uint32_t (&a)[4], uint32_t dlo, uint32_t dhi, int sd) {
  asm volatile("{\n.reg .pred p;\n.reg .b64 db;\nsetp.ne.b32 p, %22, 0;\nmov.b64 db, {%20, %21};\n"
    "wgmma.mma_async.sync.aligned.m64n32k16.f32.bf16.bf16 {%0, %1, %2, %3, %4, %5, %6, %7, %8, %9, %10, %11, %12, %13, %14, %15}, {%16, %17, %18, %19}, db, p, 1, 1, 1;\n}\n"
    : "+f"(d[0]), "+f"(d[1]), "+f"(d[2]), "+f"(d[3]), "+f"(d[4]), "+f"(d[5]), "+f"(d[6]), "+f"(d[7]), "+f"(d[8]), "+f"(d[9]), "+f"(d[10]), "+f"(d[11]), "+f"(d[12]), "+f"(d[13]), "+f"(d[14]), "+f"(d[15])
    : "r"(a[0]), "r"(a[1]), "r"(a[2]), "r"(a[3]), "r"(dlo), "r"(dhi), "r"(sd));
}
constexpr uint32_t DHI_SW128 = 0x40000040u;

__device__ __forceinline__ void poll_tags(const uint4* p, uint32_t tag, bool sel) {
  int it = 0;
  while (true) {
    uint32_t v = tag;
    if (sel) v = ld_rlx32(p);
    if (__all_sync(0xffffffffu, ((v ^ tag) & 1u) == 0u) || ++it >= SPIN) break;
  }
}

__device__ __forceinline__ void bulk_s2g(void* dst, uint32_t src, uint32_t bytes) {
  asm volatile("cp.async.bulk.global.shared::cta.bulk_group [%0], [%1], %2;" ::"l"(dst), "r"(src), "r"(bytes) : "memory");
}

__device__ __forceinline__ uint32_t tagdiff2(uint32_t a, uint32_t b, uint32_t t) {
  uint32_t d; asm("lop3.b32 %0, %1, %2, %3, 0x7e;" : "=r"(d) : "r"(a), "r"(b), "r"(t)); return d;
}
#define LDS_CHUNK(A, K0, NK, TB)                                                                           \
  _Pragma("unroll") for (int q_ = 0; q_ < NK; q_++) lds128(A[K0 + q_], (TB) + (K0 + q_) * 2048);
__device__ __noinline__ void fix_vectors(uint32_t tb, const uint4* gsrc, int n, uint32_t tag) {
  for (int q = 0; q < n; q++) {
    uint32_t cur;
    asm volatile("ld.shared.u32 %0, [%1];" : "=r"(cur) : "r"(tb + q * 2048) : "memory");
    if ((cur ^ tag) & 1u) {
      uint4 v; int it = 0;
      do { v = ld_rlx(gsrc + q * 128); } while (((v.x ^ tag) & 1u) && ++it < SPIN);
      sts128(tb + q * 2048, v);
    }
    __syncwarp();
  }
}
#define CHECK_CHUNK(A, K0, NK, TB, GSRC)                                                                   \
  {                                                                                                        \
    uint32_t bad = 0;                                                                                      \
    _Pragma("unroll") for (int q_ = 0; q_ < NK; q_ += 2) bad |= tagdiff2(A[K0 + q_][0], A[K0 + q_ + 1][0], tag); \
    if (__builtin_expect(__any_sync(0xffffffffu, bad & 1u), 0)) {                                          \
      fix_vectors((TB) + (K0) * 2048, (GSRC) + (K0) * 128, NK, tag);                                       \
      LDS_CHUNK(A, K0, NK, TB)                                                                             \
    }                                                                                                      \
  }
#define LN_LOAD()                                                                                          \
  { const uint32_t sa_ = sb + OFF_STT + (c4 * 32 + w4 * 8 + gq) * 16; lds128(v0, sa_); lds128(v1, sa_ + 2048); }
#define LN_STATS(STG)                                                                                      \
  {                                                                                                        \
    if (__builtin_expect(__any_sync(0xffffffffu, tagdiff2(v0[0], v1[0], tag) & 1u), 0)) {                   \
      const uint4* p_ = (STG) + c4 * 32 + w4 * 8 + gq; uint4 u0, u1; int it_ = 0;                           \
      do { u0 = ld_rlx(p_); u1 = ld_rlx(p_ + 128); } while ((((u0.x ^ tag) | (u1.x ^ tag)) & 1u) && ++it_ < SPIN); \
      v0[0] = u0.x; v0[1] = u0.y; v0[2] = u0.z; v0[3] = u0.w; v1[0] = u1.x; v1[1] = u1.y; v1[2] = u1.z; v1[3] = u1.w; \
      __syncwarp();                                                                                        \
    }                                                                                                      \
    float a0 = __uint_as_float(v0[0]) + __uint_as_float(v1[0]), b0 = __uint_as_float(v0[1]) + __uint_as_float(v1[1]); \
    float a1 = __uint_as_float(v0[2]) + __uint_as_float(v1[2]), b1 = __uint_as_float(v0[3]) + __uint_as_float(v1[3]); \
    _Pragma("unroll") for (int o = 1; o < 4; o <<= 1) {                                                    \
      a0 += __shfl_xor_sync(~0u, a0, o); a1 += __shfl_xor_sync(~0u, a1, o);                                \
      b0 += __shfl_xor_sync(~0u, b0, o); b1 += __shfl_xor_sync(~0u, b1, o);                                \
    }                                                                                                      \
    const float m0 = a0 * (1.f / 384.f), m1 = a1 * (1.f / 384.f);                                          \
    mm0 = pk(m0, m0); mm1 = pk(m1, m1);                                                                    \
    rs0 = rsq(fmaxf(fmaf(b0, 1.f / 384.f, -m0 * m0), 0.f) + 1e-5f);                                        \
    rs1 = rsq(fmaxf(fmaf(b1, 1.f / 384.f, -m1 * m1), 0.f) + 1e-5f);                                        \
  }
#define TILE_GEMM(WG, ACC, D0, FB, GSRC, SUB, STATS)                                                       \
  {                                                                                                        \
    mbar_wait(BAR(FB));                                                                                    \
    TSD(TSI_LANDED);                                                                                       \
    STATS(0)                                                                                               \
    LDS_CHUNK(A, 0, 6, tb)                                                                                 \
    mbar_wait(BAR((FB) + 1));                                                                              \
    STATS(1)                                                                                               \
    _Pragma("unroll") for (int g_ = 0; g_ < 4; g_++) {                                                     \
      CHECK_CHUNK(A, 6 * g_, 6, tb, GSRC)                                                                  \
      if (SUB) { HSUB_CHUNK(A, 6 * g_, 6) }                                                                \
      if (g_ < 3) { LDS_CHUNK(A, 6 * g_ + 6, 6, tb) }                                                      \
      AFENCE(A, 6 * g_, 6)                                                                                 \
      wg_fence();                                                                                          \
      _Pragma("unroll") for (int i_ = 0; i_ < 6; i_++) {                                                   \
        WG(ACC, A[6 * g_ + i_], (D0) + (6 * g_ + i_) * 128, DHI_SW128, (g_ | i_) != 0);                    \
      }                                                                                                    \
    }                                                                                                      \
    wg_commit();                                                                                           \
  }
#define HSUB_CHUNK(A, K0, NK)                                                                              \
  _Pragma("unroll") for (int q_ = K0; q_ < K0 + NK; q_++) {                                                \
    A[q_][0] = hsub2(A[q_][0], mm0); A[q_][1] = hsub2(A[q_][1], mm1);                                      \
    A[q_][2] = hsub2(A[q_][2], mm0); A[q_][3] = hsub2(A[q_][3], mm1);                                      \
  }
#define AFENCE(A, K0, NK)                                                                                  \
  _Pragma("unroll") for (int q_ = K0; q_ < K0 + NK; q_++)                                                  \
    asm volatile("" : "+r"(A[q_][0]), "+r"(A[q_][1]), "+r"(A[q_][2]), "+r"(A[q_][3])::"memory");

#define GELUH(h_) fmaf((h_), tanh_ap((h_) * fmaf((h_) * (h_), 8.f * 0.044715f * 0.7978845608028654f, 2.f * 0.7978845608028654f)), (h_))
#define PUBLISH_P8(b_, CG0, STG_)                                                                          \
  {                                                                                                        \
    const int r8_ = lane & 7, hf_ = (lane >> 3) & 1;                                                       \
    const int tau_ = 16 * w4 + 4 * (r8_ >> 1) + (r8_ & 1) + 2 * hf_;                                       \
    _Pragma("unroll") for (int e_ = 0; e_ < 4; e_++) {                                                     \
      if (4 * wg + (CG0 + e_) / 3 == c) {                                                                  \
        uint32_t x_[4]; lds128(x_, sb + OFF_RES + tid * 16 + ((CG0 + e_) % 3) * 2048);                     \
        _Pragma("unroll") for (int q_ = 0; q_ < 4; q_++) { b_[8 * e_ + 2 * q_] += blo(x_[q_]); b_[8 * e_ + 2 * q_ + 1] += bhi(x_[q_]); } \
      }                                                                                                    \
      stsm4((STG_) + tau_ * 128 + (((2 * e_ + (lane >> 4)) ^ (tau_ & 7)) << 4), pk(b_[8 * e_], b_[8 * e_ + 1]), pk(b_[8 * e_ + 2], b_[8 * e_ + 3]), \
            pk(b_[8 * e_ + 4], b_[8 * e_ + 5]), pk(b_[8 * e_ + 6], b_[8 * e_ + 7]));                       \
    }                                                                                                      \
    asm volatile("fence.proxy.async.shared::cta;" ::: "memory");                                           \
    warp_arrive(BAR(EV_P0 + 3 * wg + (CG0) / 4), lane);                                                    \
  }

#define POFF_ARG
#define POFF_PASS
__device__ __forceinline__ void attention_half(int half, uint32_t sb, uint32_t bar0, int tid, const uint4* qsrc, uint32_t tag,
                                               float (&o)[24], float& mx0, float& mx1, float& l0, float& l1 POFF_ARG) {
  uint32_t Qf[6][4], Pf[8][4];
  float sa[64];
  const float cs = 0.10206207261596577f * 1.4426950408889634f;
  const uint32_t dK = (((sb + 2 * SLOT) >> 4) | (8u << 16)) + half * 1536;
  const uint32_t dV = (((sb + SLOT) >> 4) | (48u << 16)) + half * 768;
  const uint32_t qb = sb + SLOT + 24576 + tid * 16;
  mbar_wait(bar0 + FQ * 8);
  TS(32);
  LDS_CHUNK(Qf, 0, 6, qb)
  CHECK_CHUNK(Qf, 0, 6, qb, qsrc)
  mbar_wait(bar0 + (FK0 + half) * 8);
  TS(33);
  AFENCE(Qf, 0, 6)
  wg_fence();
#pragma unroll
  for (int ks = 0; ks < 6; ks++) wg128_n(sa, Qf[ks], dK + ks * 16, 96u, ks != 0);
  wg_commit();
  wg_wait<0>();
  TS(34);
  reg_fence(sa);
  float n0[4], n1[4];
#pragma unroll
  for (int q = 0; q < 4; q++) {
    n0[q] = fmaxf(fmaxf(fmaxf(sa[16 * q], sa[16 * q + 1]), fmaxf(sa[16 * q + 4], sa[16 * q + 5])), fmaxf(fmaxf(sa[16 * q + 8], sa[16 * q + 9]), fmaxf(sa[16 * q + 12], sa[16 * q + 13])));
    n1[q] = fmaxf(fmaxf(fmaxf(sa[16 * q + 2], sa[16 * q + 3]), fmaxf(sa[16 * q + 6], sa[16 * q + 7])), fmaxf(fmaxf(sa[16 * q + 10], sa[16 * q + 11]), fmaxf(sa[16 * q + 14], sa[16 * q + 15])));
  }
  mx0 = fmaxf(fmaxf(n0[0], n0[1]), fmaxf(n0[2], n0[3])); mx1 = fmaxf(fmaxf(n1[0], n1[1]), fmaxf(n1[2], n1[3]));
  mx0 = fmaxf(mx0, __shfl_xor_sync(~0u, mx0, 1)); mx1 = fmaxf(mx1, __shfl_xor_sync(~0u, mx1, 1));
  mx0 = fmaxf(mx0, __shfl_xor_sync(~0u, mx0, 2)); mx1 = fmaxf(mx1, __shfl_xor_sync(~0u, mx1, 2));
  const float o0 = -mx0 * cs, o1 = -mx1 * cs;
  float t0[2] = {0.f, 0.f}, t1[2] = {0.f, 0.f};
#pragma unroll
  for (int e = 0; e < 16; e++) {
    sa[4 * e] = ex2(fmaf(sa[4 * e], cs, o0)); sa[4 * e + 1] = ex2(fmaf(sa[4 * e + 1], cs, o0));
    sa[4 * e + 2] = ex2(fmaf(sa[4 * e + 2], cs, o1)); sa[4 * e + 3] = ex2(fmaf(sa[4 * e + 3], cs, o1));
    t0[e & 1] += sa[4 * e] + sa[4 * e + 1]; t1[e & 1] += sa[4 * e + 2] + sa[4 * e + 3];
  }
#pragma unroll
  for (int e = 0; e < 8; e++) {
    Pf[e][0] = pk(sa[8 * e], sa[8 * e + 1]); Pf[e][1] = pk(sa[8 * e + 2], sa[8 * e + 3]);
    Pf[e][2] = pk(sa[8 * e + 4], sa[8 * e + 5]); Pf[e][3] = pk(sa[8 * e + 6], sa[8 * e + 7]);
  }
  mbar_wait(bar0 + FV * 8);
  TS(35);
  AFENCE(Pf, 0, 8)
  wg_fence();
#pragma unroll
  for (int ks = 0; ks < 8; ks++) wg48_t(o, Pf[ks], dV + ks * 96, 8u, ks != 0);
  wg_commit();
  l0 = t0[0] + t0[1]; l1 = t1[0] + t1[1];
#pragma unroll
  for (int q = 1; q < 4; q <<= 1) { l0 += __shfl_xor_sync(~0u, l0, q); l1 += __shfl_xor_sync(~0u, l1, q); }
  wg_wait<0>();
  reg_fence(o);
}

__global__ void __launch_bounds__(384, 1) fused_kernel(const __grid_constant__ Params P) {
  extern __shared__ uint8_t smem_raw[];
  const uint32_t sb = (smem_u32(smem_raw) + 1023u) & ~1023u;
  const uint32_t bar0 = sb + OFF_BAR;
#define BAR(i) (bar0 + (i) * 8)
  const int w = __shfl_sync(0xffffffffu, threadIdx.x >> 5, 0), lane = threadIdx.x & 31;
  const int g = blockIdx.x >> 3, c = blockIdx.x & 7, h = c >> 1, j = c & 1;
  Scratch* S = &g_s;
  TS(0);
  if (w == 9) {
    if (lane == 0) {
      mbar_init(BAR(FX), 1); mbar_init(BAR(FW0), 1); mbar_init(BAR(FW0 + 1), 1); mbar_init(BAR(FW0 + 2), 1); mbar_init(BAR(FWH), 1); mbar_init(BAR(FWH + 1), 1);
      asm volatile("fence.proxy.async.shared::cta;" ::: "memory");
      mbar_expect(BAR(FX), 49152);
#pragma unroll
      for (int i = 0; i < 6; i++) tma3d(sb + i * 8192, &P.tm_x, i * 64, 0, g * 16, BAR(FX));
      const int cw = 96 * h + ((h & 1) ? 32 : 0), cn = 96 * h + ((h & 1) ? 0 : 64);
#pragma unroll
      for (int b = 0; b < 3; b++) {
        const bool wide = (b < 2) == (j == 0);
        const CUtensorMap* tm = wide ? &P.tm_wqt : &P.tm_wqt32;
        const int x0 = b * 384 + (wide ? cw : cn);
        const uint32_t half = wide ? 24576u : 12288u;
        if (b < 2) {
          mbar_expect(BAR(FW0 + b), half); mbar_expect(BAR(FWH + b), half);
          tma2d(sb + (1 + b) * SLOT, tm, x0, 0, BAR(FW0 + b));
          tma2d(sb + (1 + b) * SLOT + 24576, tm, x0, 192, BAR(FWH + b));
        } else {
          mbar_expect(BAR(FW0 + b), 2 * half);
          tma2d(sb + (1 + b) * SLOT, tm, x0, 0, BAR(FW0 + b));
          tma2d(sb + (1 + b) * SLOT + 24576, tm, x0, 192, BAR(FW0 + b));
        }
      }
    }
  } else if (w == 10) {
    if (lane == 0) {
#pragma unroll
      for (int i = 3; i < NBAR; i++)
        if (i != FX && i < FWH) mbar_init(BAR(i), (i < EV_X || i >= FWH) ? 1 : (i == EV_K || i == EV_PV) ? 8 : 4);
      asm volatile("fence.proxy.async.shared::cta;" ::: "memory");
    }
  }
  __syncthreads();

  if (w >= 8) {
    asm volatile("setmaxnreg.dec.sync.aligned.u32 40;");
    const uint32_t epoch = ld_rlx32(&S->epoch[0]);
    const uint32_t tag = (epoch + 1) & 1u;
    if (w == 8) {
      if (lane == 0) {
#pragma unroll 1
        for (int jb = 3; jb < 14; jb++) {
          int ev, gate = -1, slot, x0; const CUtensorMap* tm;
          switch (jb) {
            case 3:  ev = EV_X;  slot = 0; tm = &P.tm_wpt; x0 = 48 * c; break;
            case 4:  ev = EV_QK; gate = FT0; slot = 2; tm = &P.tm_wqs; x0 = 384 + 48 * c; break;
            case 5:  ev = EV_V;  slot = 3; tm = &P.tm_wqs; x0 = 48 * c; break;
            case 6:  ev = EV_G2; gate = FT0 + 2; slot = 0; tm = &P.tm_wqs; x0 = 768 + 48 * c; break;
            case 7:  ev = EV_QS; gate = FV; slot = 3; tm = &P.tm_wps; x0 = 48 * c; break;
            case 8:  ev = EV_VS; slot = 0; tm = &P.tm_w1; x0 = 192 * c; break;
            case 9:  ev = EV_K;  gate = FT0 + 4; slot = 2; tm = &P.tm_w1; x0 = 192 * c + 64; break;
            case 10: ev = EV_G4; gate = FT0 + 6; slot = 3; tm = &P.tm_w1; x0 = 192 * c + 128; break;
            case 11: ev = EV_T4; slot = 1; tm = &P.tm_w2; x0 = 0; break;
            case 12: ev = EV_M0; slot = 0; tm = &P.tm_w2; x0 = 64; break;
            default: ev = EV_M0; slot = 2; tm = &P.tm_w2; x0 = 128; break;
          }
          if (gate >= 0) mbar_wait(BAR(gate));
          mbar_wait(BAR(ev));
          mbar_expect(BAR(FW0 + jb), jb < 8 ? 36864u : 49152u);
          tma2d(sb + slot * SLOT, tm, x0, jb < 11 ? 0 : 192 * c, BAR(FW0 + jb));
          tma2d(sb + slot * SLOT + 24576, tm, jb < 11 ? x0 : x0 + 192, jb < 11 ? 192 : 192 * c, BAR(FW0 + jb));
        }
      }
    } else if (w == 9) {
#pragma unroll 1
      for (int jb = 0; jb < 5; jb++) {
        int ev, fb; const uint4* src; const uint4* pol; const uint4* st = nullptr; uint32_t dst = sb + SLOT, bytes = 24576;
        const int pidx = (3 * (lane >> 2) + 2) * 128 + (lane & 3) * 32 + 31;
        switch (jb) {
          case 0: { ev = EV_QK; fb = FT0; src = &S->OT[g][0][0];
                    const int sh = lane >> 3, sj = (lane >> 2) & 1;
                    const int last = 6 * sh + (sj == 0 ? ((sh & 1) ? 1 : 5) : ((sh & 1) ? 5 : 3));
                    pol = src + last * 128 + (lane & 3) * 32 + 31; break; }
          case 1: ev = EV_T1; fb = FT0 + 2; src = &S->X1[g][0][0]; st = &S->ST[0][g][0][0]; pol = st + (lane >> 2) * 32 + (lane & 3) * 8 + 7; break;
          case 2: ev = EV_T2; fb = FQ; src = &S->Q[g][h][0][0]; dst += 24576; bytes = 12288;
                  pol = src + (3 * (lane >> 4) + 2) * 128 + ((lane >> 2) & 3) * 32 + (lane & 3) * 8 + 7; break;
          case 3: ev = EV_PV; fb = FT0 + 4; src = &S->OS[g][0][0]; pol = src + pidx; break;
          default: ev = EV_T3; fb = FT0 + 6; src = &S->X2[g][0][0]; st = &S->ST[1][g][0][0]; pol = st + (lane >> 2) * 32 + (lane & 3) * 8 + 7; break;
        }
        if (jb != 2) bytes = 12288;
        if (lane == 0) { mbar_expect(BAR(fb), bytes + (st ? 4096u : 0u)); if (jb != 2) mbar_expect(BAR(fb + 1), 36864); }
        poll_tags(pol, tag, (lane & 3) >= 2);
        TSD(50 + jb);
        mbar_wait(BAR(ev));
        if (lane == 0) {
          if (st) bulk_g2s(sb + OFF_STT, st, 4096, BAR(fb));
          bulk_g2s(dst, src, bytes, BAR(fb));
          if (jb != 2) bulk_g2s(dst + 12288, src + 768, 36864, BAR(fb + 1));
        }
        __syncwarp();
      }
    } else if (w == 10) {
      const int tb = g >> 2;
      const uint32_t target = 32u * (epoch + 1);
      if (lane == 0) {
        mbar_expect(BAR(FK0), 24576); mbar_expect(BAR(FK1), 24576); mbar_expect(BAR(FV), 24576);
        int it = 0;
        while ((int)(ld_rlx32(&S->KF[h][0]) - target) < 0 && ++it < SPIN) {}
        TS(56);
        mbar_wait(BAR(EV_KS));
        bulk_g2s(sb + 2 * SLOT, &S->K[tb][h][0], 24576, BAR(FK0));
        bulk_g2s(sb + 2 * SLOT + 24576, &S->K[tb][h][1536], 24576, BAR(FK1));
        it = 0;
        while ((int)(ld_rlx32(&S->KF[h][16]) - target) < 0 && ++it < SPIN) {}
        TS(57);
        mbar_wait(BAR(EV_T2));
        bulk_g2s(sb + SLOT, &S->V[tb][h][j][0], 24576, BAR(FV));
      }
    } else {
#pragma unroll
      for (int i = 0; i < 4; i++) st_rlx(&S->SC[g][c][i * 32 + lane], tag ^ 1u, 0u, 0u, 0u);
      asm volatile("bar.arrive 1, 288;" ::: "memory");
      mbar_wait(BAR(FX));
      if (lane >= 1 && lane < 6) {
        const uint32_t sz = lane == 1 ? 2304u : lane == 2 ? 6912u : lane == 3 ? 2304u : 9216u;
        const char* wp = lane == 1 ? P.wraw[1] : lane == 2 ? P.wraw[2] : lane == 3 ? P.wraw[3] : lane == 4 ? P.wraw[4] : P.wraw[5];
        asm volatile("cp.async.bulk.prefetch.L2.global [%0], %1;" ::"l"(wp + (size_t)blockIdx.x * sz), "r"(sz) : "memory");
      }
      __syncwarp();
      asm volatile("bar.sync 12, 160;" ::: "memory");
      if (lane == 0) {
        asm volatile("fence.acq_rel.gpu;" ::: "memory");
        asm volatile("st.relaxed.gpu.global.u32 [%0], %1;" ::"l"(&S->OF[g][c]), "r"(epoch + 1) : "memory");
      }
      __syncwarp();
#pragma unroll 1
      for (int kv = 0; kv < 2; kv++) {
        if (kv == 0) asm volatile("bar.sync 2, 160;" ::: "memory"); else asm volatile("bar.sync 3, 160;" ::: "memory");
        if (lane < 8) {
          const int t = lane >> 1, kb = 2 * g + (lane & 1);
          uint4* dst = kv == 0 ? &S->K[t][h][(kb * 12 + 6 * j) * 8] : &S->V[t][h][j][kb * 48];
          bulk_s2g(dst, sb + (kv == 0 ? OFF_KST : OFF_VST) + lane * 784, 768);
          asm volatile("cp.async.bulk.commit_group;" ::: "memory");
          asm volatile("cp.async.bulk.wait_group 0;" ::: "memory");
        }
        __syncwarp();
        if (lane == 0) asm volatile("red.relaxed.gpu.global.add.u32 [%0], 1;" ::"l"(kv == 0 ? &S->KF[h][0] : &S->KF[h][16]) : "memory");
      }
      asm volatile("bar.sync 4, 160;" ::: "memory");
      if (lane == 0) {
        asm volatile("fence.acq_rel.gpu;" ::: "memory");
        asm volatile("st.relaxed.gpu.global.u32 [%0], %1;" ::"l"(&S->XF[g][c][0]), "r"(epoch + 1) : "memory");
      }
      __syncwarp();
    }
    if (w >= 10) {
      const int pw = w - 10;
      {
        int it = 0; uint32_t v = epoch + 1;
        do { if (lane < 8) asm volatile("ld.acquire.gpu.global.u32 %0, [%1];" : "=r"(v) : "l"(&S->OF[g][lane]) : "memory"); } while (!__all_sync(0xffffffffu, v == epoch + 1) && ++it < SPIN);
        asm volatile("fence.proxy.async;" ::: "memory");
      }
#pragma unroll 1
      for (int i = 0; i < 3; i++) {
        mbar_wait(BAR(EV_P0 + 3 * pw + i));
        if (lane == 0) {
          const uint32_t reg = (i == 0 ? SLOT : i == 1 ? 0u : 2 * SLOT) + pw * 24576u;
          asm volatile("cp.reduce.async.bulk.tensor.2d.global.shared::cta.add.tile.bulk_group [%0, {%2, %3}], [%1];"
                       ::"l"(&P.tm_out), "r"(sb + reg), "r"(192 * pw + 64 * i), "r"((g >> 2) * 256 + (g & 3) * 64) : "memory");
          asm volatile("cp.async.bulk.commit_group;" ::: "memory");
        }
        __syncwarp();
      }
      if (lane == 0) asm volatile("cp.async.bulk.wait_group.read 0;" ::: "memory");
      if (blockIdx.x == 0 && w == 10 && lane == 0) S->epoch[0] = epoch + 1;
      TS(48);
    }
    TS_DUMP();
  } else {
  asm volatile("setmaxnreg.inc.sync.aligned.u32 232;");
  const int wg = w >> 2, w4 = w & 3, tid = threadIdx.x & 127;
  const int gq = lane >> 2, c4 = lane & 3;
  uint32_t tag = 0, epoch = 0;
  uint32_t A[24][4];
  uint32_t res[3][4];
  float acc0[24], acc1[24], acc2[24];
  float rs0 = 0.f, rs1 = 0.f;
  uint32_t mm0 = 0, mm1 = 0;
  const int gC = 4 * (gq & 3) + (g >> 2);
  const int tidC = 32 * (g & 3) + 4 * (2 * w4 + (gq >> 2)) + c4;
  const uint32_t tb = sb + SLOT + tid * 16;

  if (wg == 1) {
    {
      asm volatile("bar.sync 10, 256;" ::: "memory");
      const int row = w4 * 16 + (lane & 7) + ((lane >> 3) & 1) * 8;
      const uint32_t rb = sb + row * 128;
      float su[4] = {0, 0, 0, 0}, d1[4] = {0, 0, 0, 0}, d2[4] = {0, 0, 0, 0};
#pragma unroll 4
      for (int ks = 0; ks < 24; ks++) {
        uint32_t a[4];
        ldsm4(a, rb + (ks >> 2) * 8192 + ((((ks & 3) * 2 + (lane >> 4)) ^ (row & 7)) << 4));
        hmma(su, a[0], a[1], a[2], a[3], 0x3f803f80u, 0x3f803f80u);
        hmma(d1, a[0], a[1], a[2], a[3], a[0], a[2]);
        hmma(d2, a[0], a[1], a[2], a[3], a[1], a[3]);
      }
      float q0 = (gq & 1) ? d1[1] : d1[0], q1 = (gq & 1) ? d2[3] : d2[2];
      if ((lane & 3) == (gq >> 1)) {
        float m0 = su[0] * (1.f / 384.f), m1 = su[2] * (1.f / 384.f);
        float r0 = rsqrtf(fmaxf(q0 * (1.f / 384.f) - m0 * m0, 0.f) + 1e-5f), r1 = rsqrtf(fmaxf(q1 * (1.f / 384.f) - m1 * m1, 0.f) + 1e-5f);
        asm volatile("st.shared.f32 [%0], %1;" ::"r"(sb + OFF_RSTD + (w4 * 16 + gq) * 4), "f"(r0) : "memory");
        asm volatile("st.shared.f32 [%0], %1;" ::"r"(sb + OFF_RSTD + (w4 * 16 + gq + 8) * 4), "f"(r1) : "memory");
      }
      warp_arrive(BAR(EV_X), lane);
      asm volatile("bar.arrive 1, 288;" ::: "memory");
    }
    {
      uint4* o4 = reinterpret_cast<uint4*>(P.out);
#pragma unroll
      for (int i = 0; i < 3; i++) {
        const int q = tid + 128 * i, r = q / 6;
        st_rlx(o4 + (size_t)((g >> 2) * 256 + (g & 3) * 64 + r) * 48 + 6 * c + q - 6 * r, 0u, 0u, 0u, 0u);
      }
      asm volatile("bar.arrive 12, 160;" ::: "memory");
    }
    epoch = ld_rlx32(&S->epoch[0]);
    tag = (epoch + 1) & 1u;
  } else
  {
      mbar_wait(BAR(FX));
      TS(1);
      const int row = w4 * 16 + (lane & 7) + ((lane >> 3) & 1) * 8;
      const uint32_t rb = sb + row * 128;
      const int hi = lane >> 4, r7 = row & 7;
#pragma unroll
      for (int ks = 0; ks < 24; ks++) ldsm4(A[ks], rb + (ks >> 2) * 8192 + ((((ks & 3) * 2 + hi) ^ r7) << 4));
#pragma unroll
      for (int i = 0; i < 3; i++) { int ks = 3 * c + i; ldsm4(res[i], rb + (ks >> 2) * 8192 + ((((ks & 3) * 2 + hi) ^ r7) << 4)); }
      float su[4][4] = {{0, 0, 0, 0}, {0, 0, 0, 0}, {0, 0, 0, 0}, {0, 0, 0, 0}};
#pragma unroll
      for (int ks = 0; ks < 24; ks++) hmma(su[ks & 3], A[ks][0], A[ks][1], A[ks][2], A[ks][3], 0x3f803f80u, 0x3f803f80u);
      asm volatile("bar.arrive 10, 256;" ::: "memory");
      const float m0 = ((su[0][0] + su[1][0]) + (su[2][0] + su[3][0])) * (1.f / 384.f);
      const float m1 = ((su[0][2] + su[1][2]) + (su[2][2] + su[3][2])) * (1.f / 384.f);
      mm0 = pk(m0, m0); mm1 = pk(m1, m1);
    TS(2);
    HSUB_CHUNK(A, 0, 24)
    AFENCE(A, 0, 24)
#define TEMPORAL(NQ, NV, WGQ, WGV, KS0)                                                                    \
  {                                                                                                        \
    float aq[NQ / 2], ak[NQ / 2], av[NV / 2];                                                              \
    const uint32_t d0 = ((sb + SLOT) >> 4) | 0x10000u, d1 = ((sb + 2u * SLOT) >> 4) | 0x10000u, d2 = ((sb + 3u * SLOT) >> 4) | 0x10000u; \
    mbar_wait(BAR(0));                                                                                     \
    wg_fence();                                                                                            \
    _Pragma("unroll") for (int ks = 0; ks < 12; ks++) WGQ(aq, A[ks], d0 + ks * 128, DHI_SW128, ks != 0);   \
    mbar_wait(BAR(FWH));                                                                                   \
    wg_fence();                                                                                            \
    _Pragma("unroll") for (int ks = 12; ks < 24; ks++) WGQ(aq, A[ks], d0 + ks * 128, DHI_SW128, 1);        \
    wg_commit();                                                                                           \
    TS(4);                                                                                                 \
    mbar_wait(BAR(1));                                                                                     \
    wg_fence();                                                                                            \
    _Pragma("unroll") for (int ks = 0; ks < 12; ks++) WGQ(ak, A[ks], d1 + ks * 128, DHI_SW128, ks != 0);   \
    mbar_wait(BAR(FWH + 1));                                                                               \
    wg_fence();                                                                                            \
    _Pragma("unroll") for (int ks = 12; ks < 24; ks++) WGQ(ak, A[ks], d1 + ks * 128, DHI_SW128, 1);        \
    wg_commit();                                                                                           \
    epoch = ld_rlx32(&S->epoch[0]);                                                                        \
    mbar_wait(BAR(2));                                                                                     \
    wg_fence();                                                                                            \
    _Pragma("unroll") for (int ks = 0; ks < 6; ks++) WGV(av, A[ks], d2 + ks * 128, DHI_SW128, ks != 0);    \
    wg_commit();                                                                                           \
    asm volatile("bar.sync 1, 288;" ::: "memory");                                                         \
    tag = (epoch + 1) & 1u;                                                                                \
    asm volatile("ld.shared.f32 %0, [%1];" : "=f"(rs0) : "r"(sb + OFF_RSTD + (w4 * 16 + gq) * 4));         \
    asm volatile("ld.shared.f32 %0, [%1];" : "=f"(rs1) : "r"(sb + OFF_RSTD + (w4 * 16 + gq + 8) * 4));     \
    wg_wait<1>();                                                                                          \
    TS(5);                                                                                                 \
    reg_fence(aq); reg_fence(ak);                                                                          \
    float s1[4] = {0, 0, 0, 0}, s2[4] = {0, 0, 0, 0};                                                      \
    _Pragma("unroll") for (int i = 0; i < NQ / 16; i++) {                                                  \
      uint32_t q0 = pk(aq[8 * i] * rs0, aq[8 * i + 1] * rs0), q1 = pk(aq[8 * i + 2] * rs1, aq[8 * i + 3] * rs1);         \
      uint32_t q2 = pk(aq[8 * i + 4] * rs0, aq[8 * i + 5] * rs0), q3 = pk(aq[8 * i + 6] * rs1, aq[8 * i + 7] * rs1);     \
      uint32_t k0 = pk(ak[8 * i] * rs0, ak[8 * i + 1] * rs0), k1 = pk(ak[8 * i + 2] * rs1, ak[8 * i + 3] * rs1);         \
      uint32_t k2 = pk(ak[8 * i + 4] * rs0, ak[8 * i + 5] * rs0), k3 = pk(ak[8 * i + 6] * rs1, ak[8 * i + 7] * rs1);     \
      hmma(s1, q0, q1, q2, q3, k0, k2);                                                                    \
      hmma(s2, q0, q1, q2, q3, k1, k3);                                                                    \
    }                                                                                                      \
    st_rlx(&S->SC[g][c][tid], (__float_as_uint(s1[0]) & ~1u) | tag, __float_as_uint(s1[1]), __float_as_uint(s2[2]), __float_as_uint(s2[3])); \
    _Pragma("unroll") for (int ks = 6; ks < 24; ks++) WGV(av, A[ks], d2 + ks * 128, DHI_SW128, 1);         \
    wg_commit();                                                                                           \
    warp_arrive(BAR(EV_QK), lane);                                                                         \
    wg_wait<0>();                                                                                          \
    TS(7);                                                                                                 \
    reg_fence(av);                                                                                         \
    uint32_t vb[NV / 8][2];            \
    _Pragma("unroll") for (int jb = 0; jb < NV / 8; jb++) {                                                \
      vb[jb][0] = movm(pk(av[4 * jb] * rs0, av[4 * jb + 1] * rs0)); vb[jb][1] = movm(pk(av[4 * jb + 2] * rs1, av[4 * jb + 3] * rs1)); \
    }                                                                                                      \
    uint4 o4; int it = 0;                                                                                  \
    do { o4 = ld_rlx(&S->SC[g][c ^ 1][tid]); } while (((o4.x ^ tag) & 1u) && ++it < SPIN);                 \
    TS(6);                                                                                                 \
                          \
    float me0 = __uint_as_float((__float_as_uint(s1[0]) & ~1u) | tag);                                     \
    const float cs = 0.10206207261596577f * 1.4426950408889634f;                                           \
    float e0 = (me0 + __uint_as_float(o4.x)) * cs, e1 = (s1[1] + __uint_as_float(o4.y)) * cs;              \
    float e2 = (s2[2] + __uint_as_float(o4.z)) * cs, e3 = (s2[3] + __uint_as_float(o4.w)) * cs;            \
    float mx0 = fmaxf(e0, e1), mx1 = fmaxf(e2, e3);                                                        \
    mx0 = fmaxf(mx0, __shfl_xor_sync(~0u, mx0, 1)); mx1 = fmaxf(mx1, __shfl_xor_sync(~0u, mx1, 1));        \
    e0 = ex2(e0 - mx0); e1 = ex2(e1 - mx0); e2 = ex2(e2 - mx1); e3 = ex2(e3 - mx1);                        \
    float l0 = e0 + e1, l1 = e2 + e3;                                                                      \
    l0 += __shfl_xor_sync(~0u, l0, 1); l1 += __shfl_xor_sync(~0u, l1, 1);                                  \
    const bool valid = (c4 >> 1) == (gq >> 2);                                                             \
    const float i0 = __fdividef(1.f, l0), i1 = __fdividef(1.f, l1);                                        \
    const uint32_t p0 = valid ? pk(e0 * i0, e1 * i0) : 0u, p3 = valid ? pk(e2 * i1, e3 * i1) : 0u;         \
    uint32_t ow[NV / 8][2];                                                                                \
    _Pragma("unroll") for (int jb = 0; jb < NV / 8; jb++) {                                                \
      float o[4] = {0, 0, 0, 0};                                                                           \
      hmma(o, p0, 0u, 0u, p3, vb[jb][0], vb[jb][1]);                                                       \
      ow[jb][0] = pk(o[0], o[1]); ow[jb][1] = pk(o[2], o[3]);                                              \
    }                                                                                                      \
    _Pragma("unroll") for (int i = 0; i < NV / 16; i++)                                                    \
      st_rlx(&S->OT[g][(KS0) + i][tid], (ow[2 * i][0] & ~1u) | tag, ow[2 * i][1], ow[2 * i + 1][0], ow[2 * i + 1][1]); \
    warp_arrive(BAR(EV_V), lane);                                                                          \
  }
    if (j == 0) TEMPORAL(64, 32, wg64_t, wg32_t, 6 * h + ((h & 1) ? 0 : 4))
    else TEMPORAL(32, 64, wg32_t, wg64_t, 6 * h + ((h & 1) ? 2 : 0))
  }

#pragma unroll 1
  for (int s = 1; s < 4; s++) {
    if (wg == 0) {
    TSD(2 + s * 6);
    const uint4* gsrc = &S->OT[g][0][tid] + (size_t)(s - 1) * (16 * 24 * 128);
    const uint32_t d0 = ((sb + (s == 1 ? 0u : s == 2 ? 2u : 3u) * SLOT) >> 4) | 0x10000u;
    mbar_wait(BAR(s == 1 ? 3 : s == 2 ? 4 : 7));
    uint32_t v0[4], v1[4];
    mm0 = 0u; mm1 = 0u;
#define TSI_LANDED (3 + s * 6)
#define STAGE_STATS(P_) if (s == 2) { if (P_ == 0) { LN_LOAD() } else { LN_STATS(&S->ST[0][g][0][0]) } }
    TILE_GEMM(wg48_t, acc0, d0, FT0 + (s - 1) * 2, gsrc, true, STAGE_STATS)
#undef TSI_LANDED
    warp_arrive(BAR(EV_T1 + s - 1), lane);
    TSD(4 + s * 6);

    if (s & 1) {
      wg_wait<0>();
      TSD(5 + s * 6);
      reg_fence(acc0);
      float a0 = 0.f, b0 = 0.f, a1 = 0.f, b1 = 0.f;
      uint4* dst = (s == 1 ? &S->X1[g][3 * c][tid] : &S->X2[g][3 * c][tid]);
      float x[24];
#pragma unroll
      for (int i = 0; i < 3; i++) {
        x[8 * i] = acc0[8 * i] + blo(res[i][0]); x[8 * i + 1] = acc0[8 * i + 1] + bhi(res[i][0]);
        x[8 * i + 2] = acc0[8 * i + 2] + blo(res[i][1]); x[8 * i + 3] = acc0[8 * i + 3] + bhi(res[i][1]);
        x[8 * i + 4] = acc0[8 * i + 4] + blo(res[i][2]); x[8 * i + 5] = acc0[8 * i + 5] + bhi(res[i][2]);
        x[8 * i + 6] = acc0[8 * i + 6] + blo(res[i][3]); x[8 * i + 7] = acc0[8 * i + 7] + bhi(res[i][3]);
        res[i][0] = pk(x[8 * i], x[8 * i + 1]); res[i][1] = pk(x[8 * i + 2], x[8 * i + 3]);
        res[i][2] = pk(x[8 * i + 4], x[8 * i + 5]); res[i][3] = pk(x[8 * i + 6], x[8 * i + 7]);
        st_rlx(dst + i * 128, (res[i][0] & ~1u) | tag, res[i][1], res[i][2], res[i][3]);
      }
      TSD(s == 1 ? 58 : 59);
#pragma unroll
      for (int i = 0; i < 6; i++) {
        a0 += x[4 * i] + x[4 * i + 1]; b0 = fmaf(x[4 * i], x[4 * i], fmaf(x[4 * i + 1], x[4 * i + 1], b0));
        a1 += x[4 * i + 2] + x[4 * i + 3]; b1 = fmaf(x[4 * i + 2], x[4 * i + 2], fmaf(x[4 * i + 3], x[4 * i + 3], b1));
      }
#pragma unroll
      for (int o = 1; o < 4; o <<= 1) {
        a0 += __shfl_xor_sync(~0u, a0, o); b0 += __shfl_xor_sync(~0u, b0, o);
        a1 += __shfl_xor_sync(~0u, a1, o); b1 += __shfl_xor_sync(~0u, b1, o);
      }
      if (c4 == 0) st_rlx(&S->ST[s >> 1][g][c][w4 * 8 + gq], (__float_as_uint(a0) & ~1u) | tag, __float_as_uint(b0), __float_as_uint(a1), __float_as_uint(b1));
      warp_arrive(BAR(s == 1 ? EV_G2 : EV_G4), lane);
      if (s != 1) {
#pragma unroll
        for (int i = 0; i < 3; i++) sts128(sb + OFF_RES + tid * 16 + i * 2048, make_uint4(res[i][0], res[i][1], res[i][2], res[i][3]));
      }
    } else {
      const uint32_t d1 = ((sb + 3u * SLOT) >> 4) | 0x10000u, d2 = ((sb + 0u * SLOT) >> 4) | 0x10000u;
      const int sr = (lane & 7) + ((lane >> 3) & 1) * 8;
      const uint32_t sta = sb + OFF_KST + ((sr & 3) * 2 + (w4 >> 1)) * 784 + (lane >> 4) * 128 + (4 * (w4 & 1) + (sr >> 2)) * 16;
      mbar_wait(BAR(5));
      wg_fence();
#pragma unroll
      for (int ks = 0; ks < 6; ks++) wg48_t(acc1, A[ks], d1 + ks * 128, DHI_SW128, ks != 0);
      wg_commit();
      wg_wait<1>();
      TS(17);
      reg_fence(acc0);
      warp_arrive(BAR(EV_KS), lane);
#pragma unroll
      for (int i = 0; i < 3; i++)
        stsm4(sta + i * 256, pk(acc0[8 * i] * rs0, acc0[8 * i + 1] * rs0), pk(acc0[8 * i + 2] * rs1, acc0[8 * i + 3] * rs1),
              pk(acc0[8 * i + 4] * rs0, acc0[8 * i + 5] * rs0), pk(acc0[8 * i + 6] * rs1, acc0[8 * i + 7] * rs1));
      asm volatile("fence.proxy.async.shared::cta;" ::: "memory");
      asm volatile("bar.arrive 2, 160;" ::: "memory");
#pragma unroll
      for (int i = 0; i < 3; i++) st_rlx(&S->X1R[gC][c][i][tidC], res[i][0], res[i][1], res[i][2], res[i][3]);
      asm volatile("bar.arrive 4, 160;" ::: "memory");
#pragma unroll
      for (int ks = 6; ks < 24; ks++) wg48_t(acc1, A[ks], d1 + ks * 128, DHI_SW128, 1);
      wg_commit();
      mbar_wait(BAR(6));
      wg_fence();
#pragma unroll
      for (int ks = 0; ks < 6; ks++) wg48_t(acc2, A[ks], d2 + ks * 128, DHI_SW128, ks != 0);
      wg_commit();
      wg_wait<1>();
      TS(18);
      reg_fence(acc1);
      warp_arrive(BAR(EV_QS), lane);
#pragma unroll
      for (int i = 0; i < 3; i++)
        st_rlx(&S->Q[gC][h][3 * j + i][tidC], (pk(acc1[8 * i] * rs0, acc1[8 * i + 1] * rs0) & ~1u) | tag, pk(acc1[8 * i + 2] * rs1, acc1[8 * i + 3] * rs1),
               pk(acc1[8 * i + 4] * rs0, acc1[8 * i + 5] * rs0), pk(acc1[8 * i + 6] * rs1, acc1[8 * i + 7] * rs1));
#pragma unroll
      for (int ks = 6; ks < 24; ks++) wg48_t(acc2, A[ks], d2 + ks * 128, DHI_SW128, 1);
      wg_commit();
      wg_wait<0>();
      TS(19);
      reg_fence(acc2);
      warp_arrive(BAR(EV_VS), lane);
#pragma unroll
      for (int i = 0; i < 3; i++)
        stsm4(sta + (OFF_VST - OFF_KST) + i * 256, pk(acc2[8 * i] * rs0, acc2[8 * i + 1] * rs0), pk(acc2[8 * i + 2] * rs1, acc2[8 * i + 3] * rs1),
              pk(acc2[8 * i + 4] * rs0, acc2[8 * i + 5] * rs0), pk(acc2[8 * i + 6] * rs1, acc2[8 * i + 7] * rs1));
      asm volatile("fence.proxy.async.shared::cta;" ::: "memory");
      asm volatile("bar.arrive 3, 160;" ::: "memory");

    }
    }
    if (s == 2) {
      if (wg == 0) asm volatile("bar.arrive 11, 256;" ::: "memory"); else asm volatile("bar.sync 11, 256;" ::: "memory");
      float mx0, mx1, l0, l1;
      attention_half(wg, sb, bar0, tid, &S->Q[g][h][0][tid], tag, acc0, mx0, mx1, l0, l1 POFF_PASS);
      const uint32_t cb = sb + OFF_CMB + tid * 16;
      if (wg == 1) {
#pragma unroll
        for (int i = 0; i < 6; i++) sts128(cb + i * 2048, make_uint4(__float_as_uint(acc0[4 * i]), __float_as_uint(acc0[4 * i + 1]), __float_as_uint(acc0[4 * i + 2]), __float_as_uint(acc0[4 * i + 3])));
        sts128(cb + 6 * 2048, make_uint4(__float_as_uint(mx0), __float_as_uint(mx1), __float_as_uint(l0), __float_as_uint(l1)));
        asm volatile("bar.arrive 6, 256;" ::: "memory");
        __syncwarp();
        if (lane == 0) { mbar_arrive(BAR(EV_PV)); mbar_arrive(BAR(EV_K)); }
      } else {
        TS(60);
        asm volatile("bar.sync 6, 256;" ::: "memory");
      {
        const float cs = 0.10206207261596577f * 1.4426950408889634f;
        uint32_t ob[6][4], st[4];
        lds128(st, cb + 6 * 2048);
#pragma unroll
        for (int i = 0; i < 6; i++) lds128(ob[i], cb + i * 2048);
        const float y0 = __uint_as_float(st[0]), y1 = __uint_as_float(st[1]);
        const float n0 = fmaxf(mx0, y0), n1 = fmaxf(mx1, y1);
        float a0 = ex2((mx0 - n0) * cs), b0 = ex2((y0 - n0) * cs), a1 = ex2((mx1 - n1) * cs), b1 = ex2((y1 - n1) * cs);
        const float i0 = __fdividef(1.f, fmaf(l0, a0, __uint_as_float(st[2]) * b0)), i1 = __fdividef(1.f, fmaf(l1, a1, __uint_as_float(st[3]) * b1));
        a0 *= i0; b0 *= i0; a1 *= i1; b1 *= i1;
        uint32_t ow[6][2];
#pragma unroll
        for (int i = 0; i < 6; i++) {
          ow[i][0] = pk(fmaf(acc0[4 * i], a0, __uint_as_float(ob[i][0]) * b0), fmaf(acc0[4 * i + 1], a0, __uint_as_float(ob[i][1]) * b0));
          ow[i][1] = pk(fmaf(acc0[4 * i + 2], a1, __uint_as_float(ob[i][2]) * b1), fmaf(acc0[4 * i + 3], a1, __uint_as_float(ob[i][3]) * b1));
        }
#pragma unroll
        for (int i = 0; i < 3; i++) st_rlx(&S->OS[g][3 * c + i][tid], (ow[2 * i][0] & ~1u) | tag, ow[2 * i][1], ow[2 * i + 1][0], ow[2 * i + 1][1]);
      }
      TS(38);
      __syncwarp();
      if (lane == 0) { mbar_arrive(BAR(EV_PV)); mbar_arrive(BAR(EV_K)); }
      {
        const unsigned* xf = &S->XF[4 * (g & 3) + w4][c][0];
        int it = 0; uint32_t v;
        do { asm volatile("ld.acquire.gpu.global.u32 %0, [%1];" : "=r"(v) : "l"(xf) : "memory"); } while (v != epoch + 1 && ++it < SPIN);
#pragma unroll
        for (int e = 0; e < 3; e++) { const uint4 u = ld_rlx(&S->X1R[g][c][e][tid]); res[e][0] = u.x; res[e][1] = u.y; res[e][2] = u.z; res[e][3] = u.w; }
      }
      }
    }
  }

  if (wg == 0) {
    float a128[64], a64[32];
    const uint4* gsrc = &S->X2[g][0][tid];
    const uint32_t hb = sb + OFF_H + tid * 16;
    const uint32_t dp1 = (sb >> 4) | (6144u << 16);
    const uint32_t dp2 = ((sb + 3 * SLOT) >> 4) | 0x10000u;
    mbar_wait(BAR(FW0 + 8));
    mbar_wait(BAR(FW0 + 9));
    uint32_t v0[4], v1[4];
#define TSI_LANDED 27
#define MLP_STATS(P_) if (P_ == 0) { LN_LOAD() } else { LN_STATS(&S->ST[1][g][0][0]) }
    TILE_GEMM(wg128_t, a128, dp1, FT0 + 6, gsrc, true, MLP_STATS)
#undef TSI_LANDED
    warp_arrive(BAR(EV_T4), lane);
    TS(28);
    const float hs0 = 0.5f * rs0, hs1 = 0.5f * rs1;
    mbar_wait(BAR(FW0 + 10));
    wg_fence();
#pragma unroll
    for (int ks = 0; ks < 6; ks++) wg64_t(a64, A[ks], dp2 + ks * 128, DHI_SW128, ks != 0);
    wg_commit();
    wg_wait<1>();
    reg_fence(a128);
#pragma unroll
    for (int q = 0; q < 8; q++)
      sts128(hb + q * 2048, make_uint4(pk(a128[8 * q] * hs0, a128[8 * q + 1] * hs0), pk(a128[8 * q + 2] * hs1, a128[8 * q + 3] * hs1),
                                       pk(a128[8 * q + 4] * hs0, a128[8 * q + 5] * hs0), pk(a128[8 * q + 6] * hs1, a128[8 * q + 7] * hs1)));
    asm volatile("bar.arrive 7, 256;" ::: "memory");
    TS(30);
#pragma unroll
    for (int ks = 6; ks < 24; ks++) wg64_t(a64, A[ks], dp2 + ks * 128, DHI_SW128, 1);
    wg_commit();
    warp_arrive(BAR(EV_M0), lane);
    wg_wait<0>();
    reg_fence(a64);
    TS(29);
    warp_arrive(BAR(EV_M2), lane);
#pragma unroll
    for (int q = 0; q < 4; q++) {
      float y[8];
#pragma unroll
      for (int e = 0; e < 8; e++) { const float hx = a64[8 * q + e] * ((e & 2) ? hs1 : hs0); y[e] = GELUH(hx); }
      sts128(hb + (8 + q) * 2048, make_uint4(pk(y[0], y[1]), pk(y[2], y[3]), pk(y[4], y[5]), pk(y[6], y[7])));
    }
  } else {
    const uint32_t hb = sb + OFF_H + tid * 16;
    asm volatile("bar.sync 7, 256;" ::: "memory");
#pragma unroll 1
    for (int q = 0; q < 8; q += 4) {
      uint32_t r[4][4];
#pragma unroll
      for (int i = 0; i < 4; i++) lds128(r[i], hb + (q + i) * 2048);
#pragma unroll
      for (int i = 0; i < 4; i++) {
#pragma unroll
        for (int e = 0; e < 4; e++) { const float lo = blo(r[i][e]), hi = bhi(r[i][e]); r[i][e] = pk(GELUH(lo), GELUH(hi)); }
        sts128(hb + (q + i) * 2048, make_uint4(r[i][0], r[i][1], r[i][2], r[i][3]));
      }
    }
  }
  {
    const uint32_t hb = sb + OFF_H + tid * 16;
    TS(39);
    mbar_wait(BAR(FW0 + 11));
    asm volatile("bar.sync 8, 256;" ::: "memory");
    uint32_t H[12][4];
    float b1[32], b2[32], b3[32];
    const uint32_t r0 = sb + SLOT + wg * 24576u, r1 = sb + wg * 24576u, r2 = sb + 2 * SLOT + wg * 24576u;
    const uint32_t d0 = (r0 >> 4) | 0x10000u, d1 = (r1 >> 4) | 0x10000u, d2 = (r2 >> 4) | 0x10000u;
    LDS_CHUNK(H, 0, 12, hb)
    AFENCE(H, 0, 12)
    if (wg == 1) asm volatile("bar.sync 9, 256;" ::: "memory");
    wg_fence();
#pragma unroll
    for (int ks = 0; ks < 12; ks++) wg64_t(b1, H[ks], d0 + ks * 128, DHI_SW128, ks != 0);
    wg_commit();
    if (wg == 0) asm volatile("bar.arrive 9, 256;" ::: "memory");
    mbar_wait(BAR(FW0 + 12));
    wg_fence();
#pragma unroll
    for (int ks = 0; ks < 6; ks++) wg64_t(b2, H[ks], d1 + ks * 128, DHI_SW128, ks != 0);
    wg_commit();
    wg_wait<1>();
    reg_fence(b1);
    TS(40);
    PUBLISH_P8(b1, 0, r0)
#pragma unroll
    for (int ks = 6; ks < 12; ks++) wg64_t(b2, H[ks], d1 + ks * 128, DHI_SW128, 1);
    wg_commit();
    mbar_wait(BAR(FW0 + 13));
    wg_fence();
#pragma unroll
    for (int ks = 0; ks < 6; ks++) wg64_t(b3, H[ks], d2 + ks * 128, DHI_SW128, ks != 0);
    wg_commit();
    wg_wait<1>();
    reg_fence(b2);
    TS(43);
    PUBLISH_P8(b2, 4, r1)
#pragma unroll
    for (int ks = 6; ks < 12; ks++) wg64_t(b3, H[ks], d2 + ks * 128, DHI_SW128, 1);
    wg_commit();
    wg_wait<0>();
    reg_fence(b3);
    TS(44);
    PUBLISH_P8(b3, 8, r2)
    TS(45);
  }
  {
    TS_DUMP();
  }

  }
}

typedef CUresult (*EncFn)(CUtensorMap*, CUtensorMapDataType, cuuint32_t, void*, const cuuint64_t*, const cuuint64_t*, const cuuint32_t*,
                          const cuuint32_t*, CUtensorMapInterleave, CUtensorMapSwizzle, CUtensorMapL2promotion, CUtensorMapFloatOOBfill);

static void enc2d(EncFn enc, CUtensorMap* tm, const void* p, int cols, int rows, int boxc, int boxr) {
  cuuint64_t gd[2] = {(cuuint64_t)cols, (cuuint64_t)rows}; cuuint64_t gs[1] = {(cuuint64_t)cols * 2};
  cuuint32_t bd[2] = {(cuuint32_t)boxc, (cuuint32_t)boxr}; cuuint32_t es[2] = {1, 1};
  enc(tm, CU_TENSOR_MAP_DATA_TYPE_BFLOAT16, 2, const_cast<void*>(p), gd, gs, bd, es, CU_TENSOR_MAP_INTERLEAVE_NONE, CU_TENSOR_MAP_SWIZZLE_128B,
      CU_TENSOR_MAP_L2_PROMOTION_L2_128B, CU_TENSOR_MAP_FLOAT_OOB_FILL_NONE);
}

}

extern "C" void kernel_launch(void* const* d_in, const int* in_sizes, int n_in, void* d_out, int out_size) {
  using namespace vm;
  static Params P;
  static bool init = false;
  static const void* key[8];
  bool same = init;
  for (int i = 0; i < 7; i++) same = same && key[i] == d_in[i];
  same = same && key[7] == d_out;
  if (!same) {
    void* fn = nullptr; cudaDriverEntryPointQueryResult qr;
    cudaGetDriverEntryPoint("cuTensorMapEncodeTiled", &fn, cudaEnableDefault, &qr);
    EncFn enc = (EncFn)fn;
    {
      cuuint64_t gd[3] = {384, 4, 256}; cuuint64_t gs[2] = {256 * 768, 768}; cuuint32_t bd[3] = {64, 4, 16}; cuuint32_t es[3] = {1, 1, 1};
      enc(&P.tm_x, CU_TENSOR_MAP_DATA_TYPE_BFLOAT16, 3, d_in[0], gd, gs, bd, es, CU_TENSOR_MAP_INTERLEAVE_NONE, CU_TENSOR_MAP_SWIZZLE_128B,
          CU_TENSOR_MAP_L2_PROMOTION_L2_128B, CU_TENSOR_MAP_FLOAT_OOB_FILL_NONE);
    }
    enc2d(enc, &P.tm_wqt, d_in[1], 1152, 384, 64, 192);
    enc2d(enc, &P.tm_wqt32, d_in[1], 1152, 384, 32, 192);
    enc2d(enc, &P.tm_wpt, d_in[2], 384, 384, 48, 192);
    enc2d(enc, &P.tm_wqs, d_in[3], 1152, 384, 48, 192);
    enc2d(enc, &P.tm_wps, d_in[4], 384, 384, 48, 192);
    enc2d(enc, &P.tm_w1, d_in[5], 1536, 384, 64, 192);
    enc2d(enc, &P.tm_w2, d_in[6], 384, 1536, 64, 192);
    for (int i = 0; i < 6; i++) P.wraw[i] = (const char*)d_in[i + 1];
    P.out = (__nv_bfloat16*)d_out;
    {
      cuuint64_t gd[2] = {384, 1024}; cuuint64_t gs[1] = {768}; cuuint32_t bd[2] = {64, 64}; cuuint32_t es[2] = {1, 1};
      enc(&P.tm_out, CU_TENSOR_MAP_DATA_TYPE_BFLOAT16, 2, d_out, gd, gs, bd, es, CU_TENSOR_MAP_INTERLEAVE_NONE, CU_TENSOR_MAP_SWIZZLE_128B,
          CU_TENSOR_MAP_L2_PROMOTION_NONE, CU_TENSOR_MAP_FLOAT_OOB_FILL_NONE);
    }
    cudaFuncSetAttribute(fused_kernel, cudaFuncAttributeMaxDynamicSharedMemorySize, SMEM_BYTES);
    for (int i = 0; i < 7; i++) key[i] = d_in[i];
    key[7] = d_out; init = true;
  }
  fused_kernel<<<128, 384, SMEM_BYTES, cudaStreamPerThread>>>(P);
}
```
